```python
import torch

def _softmax(x, axis=-1):
    return torch.softmax(x, dim=axis)
def _gelu(x):
    return torch.nn.functional.gelu(x, approximate="tanh")
def _silu(x):
    return torch.nn.functional.silu(x)
def _sigmoid(x):
    return torch.sigmoid(x)
def _layernorm(x, axis=-1, eps=1e-5):
    m = x.mean(dim=axis, keepdim=True)
    v = x.var(dim=axis, keepdim=True, unbiased=False)
    return (x - m) / torch.sqrt(v + eps)
def _scatter_add(tgt, idx, src, axis=0):
    return tgt.clone().index_add_(axis, idx, src)
def _segment_sum(src, seg, n):
    out = torch.zeros((n,) + src.shape[1:], dtype=src.dtype)
    return out.index_add_(0, seg, src)
def _pad(x, pw):
    flat = tuple(v for pair in reversed(pw) for v in pair)
    return torch.nn.functional.pad(x, flat)

kernel_name = 'recurrent_scan__ssm_conv_s5__dense_activation_relu__prompt'

def setup_inputs():

    _w = (lambda a: (lambda t: t.to(torch.bfloat16) if t.is_floating_point() else t)(torch.as_tensor(a)))
    def _A_setup():
        B, S, D = 1, 2048, 640
        P = D
        Lambda_re = -0.5 * (lambda _x: torch.exp(torch.as_tensor(_x)))((lambda *s: torch.randn(*s, dtype=torch.bfloat16) * 0.2)(P))
        Lambda_im = (lambda *s: torch.randn(*s, dtype=torch.bfloat16) * 0.4)(P) * 1.0
        B_re = (lambda *s: torch.randn(*s, dtype=torch.bfloat16) * 0.2)(P, D) * (D ** -0.5)
        B_im = (lambda *s: torch.randn(*s, dtype=torch.bfloat16) * 0.2)(P, D) * (D ** -0.5)
        C_re = (lambda *s: torch.randn(*s, dtype=torch.bfloat16) * 0.2)(D, P) * (P ** -0.5)
        C_im = (lambda *s: torch.randn(*s, dtype=torch.bfloat16) * 0.2)(D, P) * (P ** -0.5)
        log_dt = (lambda *s: torch.randn(*s, dtype=torch.bfloat16) * 0.2)(P) * 0.3 - 2.0
        Dskip = (lambda *s: torch.randn(*s, dtype=torch.bfloat16) * 0.05)(D)
        return {
            "x": _w((lambda *s: torch.randn(*s, dtype=torch.bfloat16) * 0.05)(B, S, D)),
            "Lambda_re": _w(Lambda_re),
            "Lambda_im": _w(Lambda_im),
            "B_re": _w(B_re),
            "B_im": _w(B_im),
            "C_re": _w(C_re),
            "C_im": _w(C_im),
            "log_dt": _w(log_dt),
            "Dskip": _w(Dskip),
        }
    _A_in = _A_setup()

    def _B_setup():
        B, S, D, Dff = 1, 2048, 640, 1536
        return {
            "x": _w((lambda *s: torch.randn(*s, dtype=torch.bfloat16) * 0.05)(B, S, D)),
            "w1": _w((lambda *s: torch.randn(*s, dtype=torch.bfloat16) * 0.05)(D, Dff)),
            "w2": _w((lambda *s: torch.randn(*s, dtype=torch.bfloat16) * 0.05)(Dff, D)),
        }
    _B_in = _B_setup()

    return {
        "A_x": _A_in["x"],
        "A_Lambda_re": _A_in["Lambda_re"],
        "A_Lambda_im": _A_in["Lambda_im"],
        "A_B_re": _A_in["B_re"],
        "A_B_im": _A_in["B_im"],
        "A_C_re": _A_in["C_re"],
        "A_C_im": _A_in["C_im"],
        "A_log_dt": _A_in["log_dt"],
        "A_Dskip": _A_in["Dskip"],
        "B_x": _B_in["x"],
        "B_w1": _B_in["w1"],
        "B_w2": _B_in["w2"],
    }

def reference(A_x, A_Lambda_re, A_Lambda_im, A_B_re, A_B_im, A_C_re, A_C_im, A_log_dt, A_Dskip, B_x, B_w1, B_w2):
    def _A_ref(x, Lambda_re, Lambda_im, B_re, B_im, C_re, C_im, log_dt, Dskip):
        Bsz, L, H = x.shape
        Lam = Lambda_re + 1j * Lambda_im
        Bmat = B_re + 1j * B_im
        Cmat = C_re + 1j * C_im
        dt = torch.exp(log_dt)
        Lam_bar = torch.exp(dt * Lam)
        B_bar = ((Lam_bar - 1.0) / Lam)[:, None] * Bmat
        Bu = torch.einsum("bld,pd->blp", x + 0j, B_bar)
        h = torch.zeros_like(Bu[:, 0, :])
        hs = []
        for t in range(L):
            h = Lam_bar[None, :] * h + Bu[:, t, :]
            hs.append(h)
        hseq = torch.stack(hs, 1)
        y = 2.0 * torch.einsum("blp,dp->bld", hseq, Cmat).real + x * Dskip[None, None, :]
        return y

    def _B_ref(x, w1, w2):
        h = torch.einsum("bsd,df->bsf", x, w1)
        zero = torch.zeros_like(h)
        h = torch.maximum(h, zero)
        return torch.einsum("bsf,fd->bsd", h, w2)

    x = A_x
    xn = _layernorm(x, axis=-1)
    s = _A_ref(xn, A_Lambda_re, A_Lambda_im, A_B_re, A_B_im, A_C_re, A_C_im, A_log_dt, A_Dskip)
    g = _silu(_B_ref(xn, B_w1, B_w2))
    return x + s * g
```

```cpp
#include <cuda_runtime.h>
#include <cuda_bf16.h>
#include <cuda.h>
#include <stdint.h>

namespace {

constexpr int SEQ = 2048, DM = 640, DFF = 1536;
constexpr int N1 = 192;
constexpr int N2 = 160;
constexpr int NCTA = 132;

constexpr int SLOT = 40960, F_NSLOT = 5, S_NSLOT = 4;
constexpr int F_STAGE = SLOT * F_NSLOT;
constexpr int F_CS = F_STAGE + 24576;
constexpr int SLOT2 = 36864;
constexpr int TABP = 144;
constexpr int S_TAB0 = SLOT * S_NSLOT;
constexpr int S_STAGE = SLOT2 * 5;
constexpr int S_TAB1 = S_STAGE + 32768;
constexpr int S_STATN = S_TAB1 + 64 * TABP;
constexpr int SM_STATS = 230912;
constexpr int SM_BAR = 231936;
constexpr int SMEM_BYTES = 232448;

__device__ __align__(1024) __nv_bfloat16 g_H1[SEQ * DFF];
constexpr int HSP = SEQ + 64;
__device__ __align__(1024) __nv_bfloat16 g_Hs[2 * DM * HSP];
struct Scratch {
  uint4 simg[64 * 2 * 10 * 128];
  float2 S[16 * DM];
  uint2 stats[SEQ];
  uint2 cs[16 * 192];
  unsigned cnt[272 * 32];
};
__device__ __align__(1024) Scratch g_scr;
constexpr int C_HS = 0, C_H1 = 80, C_Y = 144;
#define ONES8 1, 1, 1, 1, 1, 1, 1, 1
#define ONES32 ONES8, ONES8, ONES8, ONES8
__device__ __align__(128) unsigned g_gen[132] = {ONES32, ONES32, ONES32, ONES32, 1, 1, 1, 1};

struct Maps { CUtensorMap x, xp, bb, w1, cre, cim, w2, h1l, hsl, h1s, hss, w1s, xf, bb0; };
struct Ptrs {
  const __nv_bfloat16 *x, *lre, *lim, *bre, *bim, *logdt, *dskip, *w1;
  float* out;
  Scratch* scr;
  unsigned* gen;
  int topo;
  uint32_t zero;
  int swap;
};

__device__ __forceinline__ uint32_t smem_u32(const void* p) { return (uint32_t)__cvta_generic_to_shared(p); }
__device__ __forceinline__ void mbar_init(uint32_t bar, uint32_t cnt) { asm volatile("mbarrier.init.shared::cta.b64 [%0], %1;" ::"r"(bar), "r"(cnt)); }
__device__ __forceinline__ void mbar_expect_tx(uint32_t bar, uint32_t bytes) { asm volatile("mbarrier.arrive.expect_tx.shared::cta.b64 _, [%0], %1;" ::"r"(bar), "r"(bytes) : "memory"); }
__device__ __forceinline__ void mbar_arrive(uint32_t bar) { asm volatile("mbarrier.arrive.shared::cta.b64 _, [%0];" ::"r"(bar) : "memory"); }
__device__ __forceinline__ void mbar_arrive_cluster(uint32_t bar, uint32_t cta) {
  asm volatile("{\n.reg .b32 ra;\nmapa.shared::cluster.u32 ra, %0, %1;\nmbarrier.arrive.shared::cluster.b64 _, [ra];\n}" ::"r"(bar), "r"(cta) : "memory");
}
__device__ __forceinline__ void mbar_wait(uint32_t bar, uint32_t parity) {
  asm volatile("{\n.reg .pred p, q;\n.reg .u32 c;\nmov.u32 c, 0x100000;\nW%=:\nmbarrier.try_wait.parity.shared::cta.b64 p, [%0], %1;\n"
               "add.u32 c, c, -1;\nsetp.ne.and.u32 q, c, 0, !p;\n@q bra W%=;\n}" ::"r"(bar), "r"(parity) : "memory");
}
__device__ __forceinline__ void mbar_wait_lazy(uint32_t bar, uint32_t parity) {
  asm volatile("{\n.reg .pred p, q;\n.reg .u32 c;\nmov.u32 c, 0x40000;\nW%=:\nmbarrier.try_wait.parity.shared::cta.b64 p, [%0], %1;\n"
               "add.u32 c, c, -1;\nsetp.ne.and.u32 q, c, 0, !p;\n@q nanosleep.u32 %2;\n@q bra W%=;\n}" ::"r"(bar), "r"(parity), "n"(128) : "memory");
}
__device__ __forceinline__ void tma2(uint32_t dst, const CUtensorMap* tm, int c0, int c1, uint32_t bar) {
  asm volatile("cp.async.bulk.tensor.2d.shared::cluster.global.mbarrier::complete_tx::bytes [%0], [%1, {%3, %4}], [%2];"
               ::"r"(dst), "l"(tm), "r"(bar), "r"(c0), "r"(c1) : "memory");
}
__device__ __forceinline__ void tma2_mc(uint32_t dst, const CUtensorMap* tm, int c0, int c1, uint32_t bar) {
  asm volatile("cp.async.bulk.tensor.2d.shared::cluster.global.mbarrier::complete_tx::bytes.multicast::cluster [%0], [%1, {%3, %4}], [%2], %5;"
               ::"r"(dst), "l"(tm), "r"(bar), "r"(c0), "r"(c1), "h"((uint16_t)3) : "memory");
}
__device__ __forceinline__ void tma3(uint32_t dst, const CUtensorMap* tm, int c0, int c1, int c2, uint32_t bar) {
  asm volatile("cp.async.bulk.tensor.3d.shared::cluster.global.mbarrier::complete_tx::bytes [%0], [%1, {%3, %4, %5}], [%2];"
               ::"r"(dst), "l"(tm), "r"(bar), "r"(c0), "r"(c1), "r"(c2) : "memory");
}
__device__ __forceinline__ void tma4(uint32_t dst, const CUtensorMap* tm, int c0, int c3, uint32_t bar) {
  asm volatile("cp.async.bulk.tensor.4d.shared::cluster.global.mbarrier::complete_tx::bytes [%0], [%1, {%3, %5, %5, %4}], [%2];"
               ::"r"(dst), "l"(tm), "r"(bar), "r"(c0), "r"(c3), "r"(0) : "memory");
}
__device__ __forceinline__ void tma4_mc(uint32_t dst, const CUtensorMap* tm, int c0, int c3, uint32_t bar) {
  asm volatile("cp.async.bulk.tensor.4d.shared::cluster.global.mbarrier::complete_tx::bytes.multicast::cluster [%0], [%1, {%3, %5, %5, %4}], [%2], %6;"
               ::"r"(dst), "l"(tm), "r"(bar), "r"(c0), "r"(c3), "r"(0), "h"((uint16_t)3) : "memory");
}
__device__ __forceinline__ void tma5_mc(uint32_t dst, const CUtensorMap* tm, int c2, int c4, uint32_t bar) {
  asm volatile("cp.async.bulk.tensor.5d.shared::cluster.global.mbarrier::complete_tx::bytes.multicast::cluster [%0], [%1, {%5, %5, %3, %5, %4}], [%2], %6;"
               ::"r"(dst), "l"(tm), "r"(bar), "r"(c2), "r"(c4), "r"(0), "h"((uint16_t)3) : "memory");
}
template <bool MC> __device__ __forceinline__ void tma_w1(uint32_t dst, const CUtensorMap* tm, int c1, int c4, uint32_t bar) {
  if (MC) asm volatile("cp.async.bulk.tensor.5d.shared::cluster.global.mbarrier::complete_tx::bytes.multicast::cluster [%0], [%1, {%5, %3, %5, %5, %4}], [%2], %6;"
               ::"r"(dst), "l"(tm), "r"(bar), "r"(c1), "r"(c4), "r"(0), "h"((uint16_t)3) : "memory");
  else asm volatile("cp.async.bulk.tensor.5d.shared::cluster.global.mbarrier::complete_tx::bytes [%0], [%1, {%5, %3, %5, %5, %4}], [%2];"
               ::"r"(dst), "l"(tm), "r"(bar), "r"(c1), "r"(c4), "r"(0) : "memory");
}
__device__ __forceinline__ void tma5_b(uint32_t dst, const CUtensorMap* tm, int c3, uint32_t bar) {
  asm volatile("cp.async.bulk.tensor.5d.shared::cluster.global.mbarrier::complete_tx::bytes [%0], [%1, {%4, %4, %4, %3, %4}], [%2];"
               ::"r"(dst), "l"(tm), "r"(bar), "r"(c3), "r"(0) : "memory");
}
__device__ __forceinline__ void tma5(uint32_t dst, const CUtensorMap* tm, int c3, int c4, uint32_t bar) {
  asm volatile("cp.async.bulk.tensor.5d.shared::cluster.global.mbarrier::complete_tx::bytes [%0], [%1, {%5, %5, %5, %3, %4}], [%2];"
               ::"r"(dst), "l"(tm), "r"(bar), "r"(c3), "r"(c4), "r"(0) : "memory");
}
__device__ __forceinline__ void tma3_st(const CUtensorMap* tm, uint32_t src, int c1, int c2) {
  asm volatile("cp.async.bulk.tensor.3d.global.shared::cta.bulk_group [%0, {%4, %2, %3}], [%1];" ::"l"(tm), "r"(src), "r"(c1), "r"(c2), "r"(0) : "memory");
}
__device__ __forceinline__ void bulk_st(void* dst, uint32_t src, uint32_t bytes) {
  asm volatile("cp.async.bulk.global.shared::cta.bulk_group [%0], [%1], %2;" ::"l"(dst), "r"(src), "r"(bytes) : "memory");
}
__device__ __forceinline__ void bulk_ld(uint32_t dst, const void* src, uint32_t bytes, uint32_t bar) {
  asm volatile("cp.async.bulk.shared::cluster.global.mbarrier::complete_tx::bytes [%0], [%1], %2, [%3];" ::"r"(dst), "l"(src), "r"(bytes), "r"(bar) : "memory");
}
__device__ __forceinline__ void bulk_commit() { asm volatile("cp.async.bulk.commit_group;" ::: "memory"); }
__device__ __forceinline__ void bulk_wait_read() { asm volatile("cp.async.bulk.wait_group.read 0;" ::: "memory"); }
__device__ __forceinline__ void bulk_wait_all() { asm volatile("cp.async.bulk.wait_group 0;" ::: "memory"); }
__device__ __forceinline__ void fence_async_smem() { asm volatile("fence.proxy.async.shared::cta;" ::: "memory"); }
__device__ __forceinline__ void fence_async_global() { asm volatile("fence.proxy.async.global;" ::: "memory"); }
__device__ __forceinline__ void prefetch_tmap(const CUtensorMap* tm) { asm volatile("prefetch.tensormap [%0];" ::"l"(tm) : "memory"); }
__device__ __forceinline__ void wg_fence() { asm volatile("wgmma.fence.sync.aligned;" ::: "memory"); }
__device__ __forceinline__ void wg_commit() { asm volatile("wgmma.commit_group.sync.aligned;" ::: "memory"); }
template <int N> __device__ __forceinline__ void wg_wait() { asm volatile("wgmma.wait_group.sync.aligned %0;" ::"n"(N) : "memory"); }
__device__ __forceinline__ void bar_sync(int id, int n) { asm volatile("bar.sync %0, %1;" ::"r"(id), "r"(n) : "memory"); }
__device__ __forceinline__ void bar_arrive(int id, int n) { asm volatile("bar.arrive %0, %1;" ::"r"(id), "r"(n) : "memory"); }
__device__ __forceinline__ bool elect_one() {
  uint32_t e;
  asm volatile("{\n.reg .pred p;\nelect.sync _|p, 0xffffffff;\nselp.u32 %0, 1, 0, p;\n}" : "=r"(e));
  return e;
}
__device__ __forceinline__ void cluster_arrive() { asm volatile("barrier.cluster.arrive.relaxed.aligned;" ::: "memory"); }
__device__ __forceinline__ void cluster_wait() { asm volatile("barrier.cluster.wait.aligned;" ::: "memory"); }
__device__ __forceinline__ void cnt_signal(Scratch* sc, int idx) {
  asm volatile("red.relaxed.gpu.global.add.u32 [%0], 1;" ::"l"(sc->cnt + idx * 32) : "memory");
}
__device__ __forceinline__ void cnt_wait(Scratch* sc, int idx, unsigned target) {
  asm volatile("{\n.reg .pred p, q;\n.reg .u32 c, v;\nmov.u32 c, 0x100000;\nW%=:\nld.relaxed.gpu.global.u32 v, [%0];\nadd.u32 c, c, -1;\n"
               "sub.u32 v, v, %1;\nsetp.lt.s32 p, v, 0;\nsetp.ne.and.u32 q, c, 0, p;\n@q bra W%=;\n}" ::"l"(sc->cnt + idx * 32), "r"(target) : "memory");
}
__device__ __forceinline__ uint64_t mkdesc(uint32_t addr16, uint32_t lbo, uint32_t sbo, uint32_t mode) {
  uint64_t d;
  asm("mov.b64 %0, {%1, %2};" : "=l"(d) : "r"(addr16 + ((lbo >> 4) << 16)), "r"((sbo >> 4) | (mode << 30)));
  return d;
}
__device__ __forceinline__ uint32_t pack_bf16(float lo, float hi) { uint32_t r; asm("cvt.rn.bf16x2.f32 %0, %1, %2;" : "=r"(r) : "f"(hi), "f"(lo)); return r; }
__device__ __forceinline__ uint32_t pack_bf16_relu(float lo, float hi) { uint32_t r; asm("cvt.rn.relu.bf16x2.f32 %0, %1, %2;" : "=r"(r) : "f"(hi), "f"(lo)); return r; }
__device__ __forceinline__ float bf_lo(uint32_t w) { return __uint_as_float(w << 16); }
__device__ __forceinline__ float bf_hi(uint32_t w) { return __uint_as_float(w & 0xffff0000u); }
__device__ __forceinline__ float bf_round(float v) { return __bfloat162float(__float2bfloat16_rn(v)); }
__device__ __forceinline__ float4 lds128(uint32_t a) { float4 v; asm volatile("ld.shared.v4.f32 {%0,%1,%2,%3}, [%4];" : "=f"(v.x), "=f"(v.y), "=f"(v.z), "=f"(v.w) : "r"(a)); return v; }
__device__ __forceinline__ float2 lds64v(uint32_t a) { float2 v; asm volatile("ld.volatile.shared.v2.f32 {%0,%1}, [%2];" : "=f"(v.x), "=f"(v.y) : "r"(a)); return v; }
__device__ __forceinline__ float4 lds2x64v(uint32_t a) { const float2 u = lds64v(a), v = lds64v(a + 8); return make_float4(u.x, u.y, v.x, v.y); }
__device__ __forceinline__ float2 lds64(uint32_t a) { float2 v; asm volatile("ld.shared.v2.f32 {%0,%1}, [%2];" : "=f"(v.x), "=f"(v.y) : "r"(a)); return v; }
__device__ __forceinline__ void sts128(uint32_t a, float4 v) { asm volatile("st.shared.v4.f32 [%0], {%1,%2,%3,%4};" ::"r"(a), "f"(v.x), "f"(v.y), "f"(v.z), "f"(v.w) : "memory"); }
__device__ __forceinline__ void sts64(uint32_t a, float2 v) { asm volatile("st.shared.v2.f32 [%0], {%1,%2};" ::"r"(a), "f"(v.x), "f"(v.y) : "memory"); }
__device__ __forceinline__ void sts32(uint32_t a, float v) { asm volatile("st.shared.f32 [%0], %1;" ::"r"(a), "f"(v) : "memory"); }
__device__ __forceinline__ float lds32(uint32_t a) { float v; asm volatile("ld.shared.f32 %0, [%1];" : "=f"(v) : "r"(a)); return v; }
__device__ __forceinline__ void sts128u(uint32_t p, uint32_t a, uint32_t b, uint32_t c, uint32_t d) {
  asm volatile("st.shared.v4.u32 [%0], {%1,%2,%3,%4};" ::"r"(p), "r"(a), "r"(b), "r"(c), "r"(d) : "memory");
}
__device__ __forceinline__ float2 cmul(float2 a, float2 b) { return make_float2(a.x * b.x - a.y * b.y, a.x * b.y + a.y * b.x); }
__device__ __forceinline__ float2 cfma(float2 a, float2 b, float2 c) {
  return make_float2(fmaf(a.x, b.x, fmaf(-a.y, b.y, c.x)), fmaf(a.x, b.y, fmaf(a.y, b.x, c.y)));
}
__device__ __forceinline__ void st_tag(uint2* p, uint32_t v, uint32_t tag) {
  asm volatile("st.relaxed.gpu.global.b64 [%0], %1;" ::"l"(p), "l"((uint64_t)v | ((uint64_t)tag << 32)) : "memory");
}
template <int NV> __device__ __forceinline__ void ld_tags(const uint2* (&ptr)[NV], uint32_t (&val)[NV], uint32_t tag) {
  int it = 0;
  uint32_t bad;
#pragma unroll 1
  do {
    uint64_t v[NV];
    bad = 0;
#pragma unroll
    for (int i = 0; i < NV; i++) asm volatile("ld.relaxed.gpu.global.b64 %0, [%1];" : "=l"(v[i]) : "l"(ptr[i]) : "memory");
#pragma unroll
    for (int i = 0; i < NV; i++) { bad |= (uint32_t)(v[i] >> 32) ^ tag; val[i] = (uint32_t)v[i]; }
  } while (__any_sync(0xffffffffu, bad != 0) && ++it < (1 << 20));
}
__device__ __forceinline__ uint32_t load_gen(const Ptrs& p) {
  uint32_t gen;
  asm volatile("ld.relaxed.gpu.global.u32 %0, [%1];" : "=r"(gen) : "l"(p.gen + blockIdx.x) : "memory");
  return gen;
}
__device__ __forceinline__ int opaque(int v) { asm volatile("" : "+r"(v)); return v; }
__device__ __forceinline__ float rcp_fast(float v) { float r; asm("rcp.approx.ftz.f32 %0, %1;" : "=f"(r) : "f"(v)); return r; }
__device__ __forceinline__ float tanh_fast(float v) { float r; asm("tanh.approx.f32 %0, %1;" : "=f"(r) : "f"(v)); return r; }

template<int TA, int TB> __device__ __forceinline__ void wgmma_n128(float (&d)[64], uint64_t da, uint64_t db, int scale_d) {
  asm volatile("{\n.reg .pred p;\nsetp.ne.b32 p, %66, 0;\n"
    "wgmma.mma_async.sync.aligned.m64n128k16.f32.bf16.bf16 "
    "{%0, %1, %2, %3, %4, %5, %6, %7, %8, %9, %10, %11, %12, %13, %14, %15, %16, %17, %18, %19, %20, %21, %22, %23, %24, %25, %26, %27, %28, %29, %30, %31, %32, %33, %34, %35, %36, %37, %38, %39, %40, %41, %42, %43, %44, %45, %46, %47, %48, %49, %50, %51, %52, %53, %54, %55, %56, %57, %58, %59, %60, %61, %62, %63}, "
    "%64, %65, p, 1, 1, %67, %68;\n}\n"
    : "+f"(d[0]), "+f"(d[1]), "+f"(d[2]), "+f"(d[3]), "+f"(d[4]), "+f"(d[5]), "+f"(d[6]), "+f"(d[7]), "+f"(d[8]), "+f"(d[9]), "+f"(d[10]), "+f"(d[11]), "+f"(d[12]), "+f"(d[13]), "+f"(d[14]), "+f"(d[15]), "+f"(d[16]), "+f"(d[17]), "+f"(d[18]), "+f"(d[19]), "+f"(d[20]), "+f"(d[21]), "+f"(d[22]), "+f"(d[23]), "+f"(d[24]), "+f"(d[25]), "+f"(d[26]), "+f"(d[27]), "+f"(d[28]), "+f"(d[29]), "+f"(d[30]), "+f"(d[31]), "+f"(d[32]), "+f"(d[33]), "+f"(d[34]), "+f"(d[35]), "+f"(d[36]), "+f"(d[37]), "+f"(d[38]), "+f"(d[39]), "+f"(d[40]), "+f"(d[41]), "+f"(d[42]), "+f"(d[43]), "+f"(d[44]), "+f"(d[45]), "+f"(d[46]), "+f"(d[47]), "+f"(d[48]), "+f"(d[49]), "+f"(d[50]), "+f"(d[51]), "+f"(d[52]), "+f"(d[53]), "+f"(d[54]), "+f"(d[55]), "+f"(d[56]), "+f"(d[57]), "+f"(d[58]), "+f"(d[59]), "+f"(d[60]), "+f"(d[61]), "+f"(d[62]), "+f"(d[63])
    : "l"(da), "l"(db), "r"(scale_d), "n"(TA), "n"(TB));
}
template<int TA, int TB> __device__ __forceinline__ void wgmma_n160(float (&d)[80], uint64_t da, uint64_t db, int scale_d) {
  asm volatile("{\n.reg .pred p;\nsetp.ne.b32 p, %82, 0;\n"
    "wgmma.mma_async.sync.aligned.m64n160k16.f32.bf16.bf16 "
    "{%0, %1, %2, %3, %4, %5, %6, %7, %8, %9, %10, %11, %12, %13, %14, %15, %16, %17, %18, %19, %20, %21, %22, %23, %24, %25, %26, %27, %28, %29, %30, %31, %32, %33, %34, %35, %36, %37, %38, %39, %40, %41, %42, %43, %44, %45, %46, %47, %48, %49, %50, %51, %52, %53, %54, %55, %56, %57, %58, %59, %60, %61, %62, %63, %64, %65, %66, %67, %68, %69, %70, %71, %72, %73, %74, %75, %76, %77, %78, %79}, "
    "%80, %81, p, 1, 1, %83, %84;\n}\n"
    : "+f"(d[0]), "+f"(d[1]), "+f"(d[2]), "+f"(d[3]), "+f"(d[4]), "+f"(d[5]), "+f"(d[6]), "+f"(d[7]), "+f"(d[8]), "+f"(d[9]), "+f"(d[10]), "+f"(d[11]), "+f"(d[12]), "+f"(d[13]), "+f"(d[14]), "+f"(d[15]), "+f"(d[16]), "+f"(d[17]), "+f"(d[18]), "+f"(d[19]), "+f"(d[20]), "+f"(d[21]), "+f"(d[22]), "+f"(d[23]), "+f"(d[24]), "+f"(d[25]), "+f"(d[26]), "+f"(d[27]), "+f"(d[28]), "+f"(d[29]), "+f"(d[30]), "+f"(d[31]), "+f"(d[32]), "+f"(d[33]), "+f"(d[34]), "+f"(d[35]), "+f"(d[36]), "+f"(d[37]), "+f"(d[38]), "+f"(d[39]), "+f"(d[40]), "+f"(d[41]), "+f"(d[42]), "+f"(d[43]), "+f"(d[44]), "+f"(d[45]), "+f"(d[46]), "+f"(d[47]), "+f"(d[48]), "+f"(d[49]), "+f"(d[50]), "+f"(d[51]), "+f"(d[52]), "+f"(d[53]), "+f"(d[54]), "+f"(d[55]), "+f"(d[56]), "+f"(d[57]), "+f"(d[58]), "+f"(d[59]), "+f"(d[60]), "+f"(d[61]), "+f"(d[62]), "+f"(d[63]), "+f"(d[64]), "+f"(d[65]), "+f"(d[66]), "+f"(d[67]), "+f"(d[68]), "+f"(d[69]), "+f"(d[70]), "+f"(d[71]), "+f"(d[72]), "+f"(d[73]), "+f"(d[74]), "+f"(d[75]), "+f"(d[76]), "+f"(d[77]), "+f"(d[78]), "+f"(d[79])
    : "l"(da), "l"(db), "r"(scale_d), "n"(TA), "n"(TB));
}
template<int TA, int TB> __device__ __forceinline__ void wgmma_n192(float (&d)[96], uint64_t da, uint64_t db, int scale_d) {
  asm volatile("{\n.reg .pred p;\nsetp.ne.b32 p, %98, 0;\n"
    "wgmma.mma_async.sync.aligned.m64n192k16.f32.bf16.bf16 "
    "{%0, %1, %2, %3, %4, %5, %6, %7, %8, %9, %10, %11, %12, %13, %14, %15, %16, %17, %18, %19, %20, %21, %22, %23, %24, %25, %26, %27, %28, %29, %30, %31, %32, %33, %34, %35, %36, %37, %38, %39, %40, %41, %42, %43, %44, %45, %46, %47, %48, %49, %50, %51, %52, %53, %54, %55, %56, %57, %58, %59, %60, %61, %62, %63, %64, %65, %66, %67, %68, %69, %70, %71, %72, %73, %74, %75, %76, %77, %78, %79, %80, %81, %82, %83, %84, %85, %86, %87, %88, %89, %90, %91, %92, %93, %94, %95}, "
    "%96, %97, p, 1, 1, %99, %100;\n}\n"
    : "+f"(d[0]), "+f"(d[1]), "+f"(d[2]), "+f"(d[3]), "+f"(d[4]), "+f"(d[5]), "+f"(d[6]), "+f"(d[7]), "+f"(d[8]), "+f"(d[9]), "+f"(d[10]), "+f"(d[11]), "+f"(d[12]), "+f"(d[13]), "+f"(d[14]), "+f"(d[15]), "+f"(d[16]), "+f"(d[17]), "+f"(d[18]), "+f"(d[19]), "+f"(d[20]), "+f"(d[21]), "+f"(d[22]), "+f"(d[23]), "+f"(d[24]), "+f"(d[25]), "+f"(d[26]), "+f"(d[27]), "+f"(d[28]), "+f"(d[29]), "+f"(d[30]), "+f"(d[31]), "+f"(d[32]), "+f"(d[33]), "+f"(d[34]), "+f"(d[35]), "+f"(d[36]), "+f"(d[37]), "+f"(d[38]), "+f"(d[39]), "+f"(d[40]), "+f"(d[41]), "+f"(d[42]), "+f"(d[43]), "+f"(d[44]), "+f"(d[45]), "+f"(d[46]), "+f"(d[47]), "+f"(d[48]), "+f"(d[49]), "+f"(d[50]), "+f"(d[51]), "+f"(d[52]), "+f"(d[53]), "+f"(d[54]), "+f"(d[55]), "+f"(d[56]), "+f"(d[57]), "+f"(d[58]), "+f"(d[59]), "+f"(d[60]), "+f"(d[61]), "+f"(d[62]), "+f"(d[63]), "+f"(d[64]), "+f"(d[65]), "+f"(d[66]), "+f"(d[67]), "+f"(d[68]), "+f"(d[69]), "+f"(d[70]), "+f"(d[71]), "+f"(d[72]), "+f"(d[73]), "+f"(d[74]), "+f"(d[75]), "+f"(d[76]), "+f"(d[77]), "+f"(d[78]), "+f"(d[79]), "+f"(d[80]), "+f"(d[81]), "+f"(d[82]), "+f"(d[83]), "+f"(d[84]), "+f"(d[85]), "+f"(d[86]), "+f"(d[87]), "+f"(d[88]), "+f"(d[89]), "+f"(d[90]), "+f"(d[91]), "+f"(d[92]), "+f"(d[93]), "+f"(d[94]), "+f"(d[95])
    : "l"(da), "l"(db), "r"(scale_d), "n"(TA), "n"(TB));
}
template<int N, int TA, int TB> __device__ __forceinline__ void wgmma(float (&d)[N/2], uint64_t da, uint64_t db, int scale_d) {
  if constexpr (N == 128) wgmma_n128<TA, TB>(d, da, db, scale_d);
  else if constexpr (N == 160) wgmma_n160<TA, TB>(d, da, db, scale_d);
  else if constexpr (N == 192) wgmma_n192<TA, TB>(d, da, db, scale_d);
}


__device__ __forceinline__ uint32_t b_full(uint32_t sb, int s) { return sb + SM_BAR + 8 * s; }
__device__ __forceinline__ uint32_t b_empty(uint32_t sb, int s) { return sb + SM_BAR + 40 + 8 * s; }
__device__ __forceinline__ uint32_t b_staged(uint32_t sb, int s) { return sb + SM_BAR + 80 + 8 * s; }
__device__ __forceinline__ uint32_t b_freed(uint32_t sb, int s) { return sb + SM_BAR + 136 + 8 * s; }
__device__ __forceinline__ uint32_t b_ready(uint32_t sb, int s) { return sb + SM_BAR + 176 + 8 * s; }
__device__ __forceinline__ uint32_t b_aux(uint32_t sb) { return sb + SM_BAR + 216; }
__device__ __forceinline__ uint32_t b_tab(uint32_t sb, int s) { return sb + SM_BAR + 224 + 8 * s; }
__device__ __forceinline__ uint32_t b_x(uint32_t sb, int s) { return sb + SM_BAR + 240 + 8 * s; }
constexpr int BAR_WG0 = 1, BAR_T1 = 3, BAR_T2 = 4, BAR_TAB = 5;

template <int N, int MB, int MODE, int NSLOT, bool DRAIN>
__device__ __forceinline__ void mma_job(float (&acc)[MB][N / 2], uint32_t sb, int n0, int nsteps, int ntotal, int narr, int turn_bar, int t) {
  constexpr int PITCH = MODE == 2 ? SLOT2 : SLOT;
  int slot = n0 % NSLOT, par = MODE == 2 ? 1 : (n0 / NSLOT) & 1, pslot = 0;
  auto release = [&](int n) {
    if (n + NSLOT < ntotal && t < narr) mbar_arrive_cluster(b_empty(sb, pslot), t & 1);
  };
#pragma unroll 1
  for (int k = 0; k < nsteps; k++) {
    const uint32_t fb = b_full(sb, slot), fp = (MODE == 2 && slot == 4) ? par ^ 1 : par;
    mbar_wait(fb, fp);
    const uint32_t s0 = ((sb & 0x3FFFF) >> 4) + slot * (PITCH >> 4);
    wg_fence();
#pragma unroll
    for (int kk = 0; kk < 4; kk++) {
      const uint64_t db = MODE == 0 ? mkdesc(s0 + 1024 + (((kk >> 1) * (N * 64) + (kk & 1) * 1024) >> 4), 2048, 512, 2)
                                    : mkdesc(s0 + (MODE == 1 ? 0 : 1024) + kk * 2, 16, 1024, 1);
#pragma unroll
      for (int m = 0; m < MB; m++) {
        const uint64_t da = MODE == 0 ? mkdesc(s0 + m * 512 + kk * 2, 16, 1024, 1)
                          : MODE == 1 ? mkdesc(s0 + 1024 + m * 512 + kk * 2, 16, 1024, 1) : mkdesc(s0 + m * 512 + kk * 128, 16, 1024, 1);
        wgmma<N, MODE == 2, MODE == 0>(acc[m], da, db, (k | kk) != 0);
      }
    }
    wg_commit();
    if (k == nsteps - 1 && turn_bar) bar_arrive(turn_bar, 256);
    wg_wait<1>();
    if (k > 0) release(n0 + k - 1);
    pslot = slot;
    if (++slot == NSLOT) { slot = 0; par ^= 1; }
  }
  if (DRAIN) {
    wg_wait<0>();
    release(n0 + nsteps - 1);
  }
}

__device__ __forceinline__ void stage_tile(const float (&a)[80], uint32_t buf, int t) {
#pragma unroll
  for (int i = 0; i < 10; i++)
    sts128u(buf + (i * 128 + t) * 16, pack_bf16(a[8 * i], a[8 * i + 1]), pack_bf16(a[8 * i + 2], a[8 * i + 3]), pack_bf16(a[8 * i + 4], a[8 * i + 5]), pack_bf16(a[8 * i + 6], a[8 * i + 7]));
}
__device__ __forceinline__ void staged(uint32_t bar, int t) {
  fence_async_smem();
  __syncwarp();
  if ((t & 31) == 0) mbar_arrive(bar);
}
__device__ __forceinline__ void add8(float (&s)[8], const uint4& v) {
  s[0] += bf_lo(v.x); s[1] += bf_hi(v.x); s[2] += bf_lo(v.y); s[3] += bf_hi(v.y);
  s[4] += bf_lo(v.z); s[5] += bf_hi(v.z); s[6] += bf_lo(v.w); s[7] += bf_hi(v.w);
}
__device__ __forceinline__ int cs_slot_b(int ch, int comp) {
  const int beta = ch >> 7, job = beta >= 3;
  return (8 + ((ch >> 5) & 3) * 2 + job) * 192 + (comp * 3 + beta - 3 * job) * 32 + (ch & 31);
}
__device__ __forceinline__ int cs_slot_w(int f) {
  const int e = f / 96;
  return ((e & 3) * 2 + (e >> 3)) * 192 + ((e >> 2) & 1) * 96 + f - e * 96;
}
__device__ __forceinline__ void helper_cta(const Ptrs& p, uint32_t sb, int h) {
  const int t = threadIdx.x, wr = t >> 4;
  const uint32_t gen = load_gen(p);
  uint4 v[3][5];
  float s[8] = {0, 0, 0, 0, 0, 0, 0, 0};
#pragma unroll 1
  for (int pass = -2; pass < 12; pass++) {
#pragma unroll
    for (int i = 0; i < 5; i++) { v[0][i] = v[1][i]; v[1][i] = v[2][i]; }
    const int nx = pass + 2;
    if (nx < 12) {
      const uint4* src = nx < 6 ? reinterpret_cast<const uint4*>((h >> 1 ? p.bim : p.bre) + (size_t)(384 + (h & 1) * 128 + min((nx >> 1) * 48 + (t >> 3), 127)) * DM) + (t & 7) + (nx & 1) * 40
                                : reinterpret_cast<const uint4*>(p.w1 + (size_t)((nx - 6) * 120 + wr) * DFF + 1024 + h * 128) + (t & 15);
      const int st = nx < 6 ? 8 : 3 * DFF, ni = nx < 11 ? 5 : (wr < 16 ? 2 : 1);
#pragma unroll
      for (int i = 0; i < 5; i++) v[2][i] = i < ni ? __ldg(src + i * st) : make_uint4(0, 0, 0, 0);
    }
    if (pass >= 0) {
#pragma unroll
      for (int i = 0; i < 5; i++) add8(s, v[0][i]);
      if (pass < 6 && (pass & 1)) {
        float a = ((s[0] + s[1]) + (s[2] + s[3])) + ((s[4] + s[5]) + (s[6] + s[7]));
#pragma unroll
        for (int o = 1; o < 8; o <<= 1) a += __shfl_xor_sync(0xffffffffu, a, o);
        const int row = 384 + (h & 1) * 128 + min((pass >> 1) * 48 + (t >> 3), 127);
        if ((t & 7) < 2 && (row >= 512 || !(t & 1)))
          st_tag(p.scr->cs + cs_slot_b(row, (h >> 1) ^ p.swap) + (t & 1) * 32, __float_as_uint(a), gen);
#pragma unroll
        for (int i = 0; i < 8; i++) s[i] = 0.f;
      }
    }
  }
  sts128(sb + t * 32, make_float4(s[0], s[1], s[2], s[3]));
  sts128(sb + t * 32 + 16, make_float4(s[4], s[5], s[6], s[7]));
  __syncthreads();
  if (t < 256) {
    float a = 0.f;
#pragma unroll
    for (int i = 0; i < 12; i++) a += lds32(sb + ((t & 1) * 12 + i) * 512 + (t >> 1) * 4);
    a += __shfl_xor_sync(0xffffffffu, a, 1);
    if (!(t & 1)) st_tag(p.scr->cs + cs_slot_w(1024 + h * 128 + (t >> 1)), __float_as_uint(a), gen);
  }
  if (t == 256) p.gen[blockIdx.x] = gen + 1;
}

__device__ __forceinline__ void ld_states(uint64_t (&a)[4], const float2* sp, int nv, uint32_t gen) {
#pragma unroll
  for (int d = 0; d < 4; d++) {
    a[d] = gen & 3u;
    if (d < nv) asm volatile("ld.relaxed.gpu.global.b64 %0, [%1];" : "=l"(a[d]) : "l"(sp - d * DM) : "memory");
  }
}
__device__ __forceinline__ bool states_bad(const uint64_t (&a)[4], uint32_t gen) {
  return __any_sync(0xffffffffu, ((((uint32_t)a[0] ^ gen) | ((uint32_t)a[1] ^ gen) | ((uint32_t)a[2] ^ gen) | ((uint32_t)a[3] ^ gen)) & 3u) != 0);
}

__device__ __forceinline__ void scan_blocks(float (&acc)[3][64], const Ptrs& p, uint32_t sb, int wg, int g, int mi, int w, int l, int q, uint32_t gen) {
  const int beta0 = wg * 3;
  const uint32_t tb = sb + (wg ? S_TAB1 : S_TAB0) + (w * 8 + l) * TABP;
  const uint32_t tb2 = wg ? tb : tb + 64 * TABP;
  float2 T[3];
  auto step = [&](float* a, int j, const float2& st, const float4& A, float2& Tc) {
    float& re = a[4 * (j >> 1) + (j & 1)];
    float& im = a[4 * (j >> 1) + 2 + (j & 1)];
    re = st.y * fmaf(st.x, A.x, re);
    im = st.y * fmaf(st.x, A.y, im);
    Tc = j ? cfma(make_float2(A.z, A.w), Tc, make_float2(re, im)) : make_float2(re, im);
  };
  float2* sp = p.scr->S + mi * DM + beta0 * 128 + g * 32 + w * 8 + l;
  auto publish = [&]() {
    float2 o[3][3];
    float4 B[3];
#pragma unroll
    for (int b = 0; b < 3; b++) {
      B[b] = lds2x64v((b == 2 ? tb2 : tb + b * 32 * TABP) + 16);
#pragma unroll
      for (int d = 0; d < 3; d++) { o[b][d].x = __shfl_up_sync(0xffffffffu, T[b].x, d + 1); o[b][d].y = __shfl_up_sync(0xffffffffu, T[b].y, d + 1); }
    }
#pragma unroll
    for (int b = 0; b < 3; b++) {
      const float2 l32 = make_float2(B[b].x, B[b].y);
      float2 E = q >= 1 ? o[b][0] : make_float2(0.f, 0.f);
      if (q >= 2) E = cfma(l32, o[b][1], E);
      if (q == 3) E = cfma(make_float2(B[b].z, B[b].w), o[b][2], E);
      const float2 S = cfma(l32, E, T[b]);
      if (q == 3 && (b < 2 || wg == 0))
        asm volatile("st.relaxed.gpu.global.b64 [%0], %1;" ::"l"(sp + b * 128), "l"((uint64_t)((__float_as_uint(S.x) & ~3u) | (gen & 3u)) | ((uint64_t)__float_as_uint(S.y) << 32)) : "memory");
      T[b] = E;
    }
  };
  const uint32_t sta = sb + S_STATN + q * 16;
  auto after = [&](uint32_t a, float v) { return a | (__float_as_uint(v) & p.zero); };
  if (p.zero == 0) {
    const float4 A0 = lds2x64v(tb), A1 = lds2x64v(tb + 32 * TABP), A2 = lds2x64v(tb2);
    constexpr int PF = 6;
    float2 st[32];
#pragma unroll
    for (int j = 0; j < PF; j++) st[j] = lds64v(sta + (j >> 1) * 64 + (j & 1) * 8);
#pragma unroll
    for (int j = 0; j < 32; j++) {
      if (j + PF < 32) st[j + PF] = lds64v((j ? after(sta, T[0].x) : sta) + ((j + PF) >> 1) * 64 + ((j + PF) & 1) * 8);
      step(acc[0], j, st[j], A0, T[0]);
      step(acc[1], j, st[j], A1, T[1]);
      step(acc[2], j, st[j], A2, T[2]);
    }
  }
  publish();
  const int nv = mi - 4 * q;
  sp -= (1 + 4 * q) * DM;
  uint64_t a[4];
#pragma unroll
  for (int b = 0; b < 3; b++) {
    if (b < 2 ? p.zero == 0 : opaque(wg) == 0) {
      const float4 cf = lds2x64v(tb + b * 32 * TABP + 32);
#pragma unroll
      for (int j = 0; j < 32; j++) {
        float& re = acc[b][4 * (j >> 1) + (j & 1)];
        float& im = acc[b][4 * (j >> 1) + 2 + (j & 1)];
        const float u = cf.y * im, v = cf.z * re;
        re = fmaf(cf.x, re, u);
        im = fmaf(cf.w, im, v);
      }
    }
    if (b == 1) ld_states(a, sp, nv, gen);
  }
#pragma unroll
  for (int b = 0; b < 3; b++) {
    if (b < 2 || opaque(wg) == 0) {
      const uint32_t tc = tb + b * 32 * TABP;
      const float2 L = lds64v(tc + 48);
      const float4 Q = lds2x64v(tc + 64 + q * 16);
      int it = 0;
#pragma unroll 1
      while (states_bad(a, gen) && ++it < (1 << 20)) ld_states(a, sp + b * 128, nv, gen);
      float2 h = make_float2(__uint_as_float((uint32_t)a[3] & ~3u), __uint_as_float((uint32_t)(a[3] >> 32)));
#pragma unroll
      for (int d = 2; d >= 0; d--) h = cfma(L, h, make_float2(__uint_as_float((uint32_t)a[d] & ~3u), __uint_as_float((uint32_t)(a[d] >> 32))));
      h = cmul(make_float2(Q.z, Q.w), h);
      {
        const float x1 = __shfl_xor_sync(0xffffffffu, h.x, 1), y1 = __shfl_xor_sync(0xffffffffu, h.y, 1), x2 = __shfl_xor_sync(0xffffffffu, h.x, 2);
        const float y2 = __shfl_xor_sync(0xffffffffu, h.y, 2), x3 = __shfl_xor_sync(0xffffffffu, h.x, 3), y3 = __shfl_xor_sync(0xffffffffu, h.y, 3);
        h.x = (h.x + x1) + (x2 + x3); h.y = (h.y + y1) + (y2 + y3);
      }
      float2 l1 = lds64v(tc + 8);
      const float4 cf = lds2x64v(tc + 32);
      h = cfma(make_float2(Q.x, Q.y), h, T[b]);
      h = make_float2(fmaf(cf.x, h.x, cf.y * h.y), fmaf(cf.z, h.x, cf.w * h.y));
      if (!p.swap) l1.y = -l1.y;
      const int beta = beta0 + b;
      if (b == 2 || wg) mbar_wait(b_freed(sb, beta - 2), 0);
      const uint32_t so = sb + S_STAGE + (beta & 1) * 16384 + (w * 8 + l) * 64 + ((q ^ (l >> 1)) << 4);
#pragma unroll
      for (int a4 = 0; a4 < 4; a4++) {
        uint32_t pr[4], pi[4];
#pragma unroll
        for (int jj = 0; jj < 4; jj++) {
          const int j = 4 * a4 + jj;
          const float2 h0 = cfma(l1, h, make_float2(acc[b][4 * j], acc[b][4 * j + 2]));
          h = cfma(l1, h0, make_float2(acc[b][4 * j + 1], acc[b][4 * j + 3]));
          pr[jj] = pack_bf16(h0.x, h.x);
          pi[jj] = pack_bf16(h0.y, h.y);
        }
        sts128u(so + a4 * 2048, pr[0], pr[1], pr[2], pr[3]);
        sts128u(so + a4 * 2048 + 8192, pi[0], pi[1], pi[2], pi[3]);
        if (a4 == 0 && b < 2) ld_states(a, sp + (b + 1) * 128, (b == 1 && wg) ? 0 : nv, gen);
      }
      staged(b_staged(sb, beta), l * 4 + q);
    }
  }
}

__global__ void __launch_bounds__(384, 1) s5_ffn_fused(const Ptrs p, const __grid_constant__ Maps maps) {
  extern __shared__ __align__(1024) uint8_t smem_raw[];
  const uint32_t sb = smem_u32(smem_raw);
  const int cl = blockIdx.x >> 1, rank = blockIdx.x & 1;
  int grp, g;
  if (p.topo == 0) { grp = (cl & 7) + ((cl >> 5) << 3); g = (cl >> 3) & 3; }
  else if (cl < 4) { grp = 15; g = cl; }
  else if (cl < 36) { grp = (cl - 4) & 7; g = (cl - 4) >> 3; }
  else { g = ((cl - 36) * 37) >> 8; grp = 8 + (cl - 36) - 7 * g; }
  const bool is_ffn = grp < 8;
  const int mi = (grp & 7) * 2 + rank;
  const int wg = __shfl_sync(0xffffffffu, threadIdx.x >> 7, 0);
  const int t = threadIdx.x & 127;
  if (cl >= 64) { helper_cta(p, sb, blockIdx.x - 128); return; }
  if (wg == 2) {
    const int wi = __shfl_sync(0xffffffffu, t >> 5, 0);
    if (wi == 1 && elect_one()) {
#pragma unroll
      for (int s = 2; s < 34; s++) mbar_init(b_full(sb, s), (s >= 5 && s < 17) ? 4 : ((s == 28 || (s == 30 && !is_ffn)) ? 2 : 1));
      asm volatile("fence.mbarrier_init.release.cluster;" ::: "memory");
    }
    if (wi == 0 && elect_one()) {
      mbar_init(b_full(sb, 0), 1);
      mbar_init(b_full(sb, 1), 1);
      asm volatile("fence.mbarrier_init.release.cluster;" ::: "memory");
      const uint32_t fb = b_full(sb, 0);
      mbar_expect_tx(fb, SLOT);
      if (is_ffn) {
        tma_w1<false>(sb + 16384, &maps.w1, 0, g, fb);
        tma2(sb, &maps.x, 0, mi * 128, fb);
        tma_w1<false>(sb + 16384 + N1 * 64, &maps.w1, 32, g, fb);
      } else {
        tma4(sb, &maps.xp, 0, mi * 64, fb);
        tma5_b(sb + 16384, &maps.bb0, g * 4, fb);
      }
    }
    __syncwarp();
    cluster_arrive();
    if (wi == 0 && is_ffn && elect_one()) {
      const uint32_t fb = b_full(sb, 1);
      mbar_expect_tx(fb, SLOT);
      tma_w1<false>(sb + SLOT + 16384, &maps.w1, 64, g, fb);
      tma2(sb + SLOT, &maps.x, 64, mi * 128, fb);
      tma_w1<false>(sb + SLOT + 16384 + N1 * 64, &maps.w1, 96, g, fb);
    }
    __syncwarp();
    asm volatile("setmaxnreg.dec.sync.aligned.u32 40;");
    cluster_wait();
    if (wi != 2 && !elect_one()) return;
    if (wi == 0) {
      int slot = is_ffn ? 2 : 1, par = 1;
      if (is_ffn) {
#pragma unroll 1
        for (int n = 2; n < 20; n++) {
          const int job = n >= 10, k = n - job * 10;
          mbar_wait(b_empty(sb, slot), par);
          const uint32_t a = sb + slot * SLOT, fb = b_full(sb, slot);
          mbar_expect_tx(fb, 16384 + N1 * 128);
          tma2(a, &maps.x, k * 64, mi * 128, fb);
          tma_w1<true>(a + 16384 + rank * (N1 * 64), &maps.w1, k * 64 + rank * 32, job * 8 + g, fb);
          if (++slot == F_NSLOT) { slot = 0; par ^= 1; }
        }
#pragma unroll 1
        for (int u = 0; u < 24; u++) {
          mbar_wait(b_empty(sb, slot), par);
          const uint32_t a = sb + slot * SLOT, fb = b_full(sb, slot);
          mbar_expect_tx(fb, 16384 + N2 * 128);
          tma5_mc(a + 16384 + rank * (N2 * 64), &maps.w2, u * 8 + rank * 4, g * (N2 / 32), fb);
          if (u == 0 || u == 6 || u == 12 || u == 18) { mbar_wait(b_ready(sb, u / 6), 0); }
          tma4(a, &maps.h1l, u * 64, mi * 16, fb);
          if (++slot == F_NSLOT) { slot = 0; par ^= 1; }
        }
        mbar_wait(b_empty(sb, 4), 1);
      } else {
#pragma unroll 1
        for (int n = 1; n < 20; n++) {
          const int job = n >= 10, k = n - job * 10;
          mbar_wait(b_empty(sb, slot), par);
          const uint32_t a = sb + slot * SLOT, fb = b_full(sb, slot);
          mbar_expect_tx(fb, job ? 32768 : 40960);
          tma4(a, &maps.xp, k * 64, mi * 64, fb);
#pragma unroll 1
          for (int b = 0; b < 3 - job; b++) tma4_mc(a + 16384 + b * 8192 + rank * 4096, &maps.bb, k * 64, (job * 3 + b) * 16 + g * 4 + rank * 2, fb);
          if (++slot == S_NSLOT) { slot = 0; par ^= 1; }
        }
        const uint32_t gen0 = load_gen(p);
#pragma unroll 1
        for (int u = 0; u < 20; u++) {
          const int im = (u >> 1) & 1, ch = (u >> 2) * 128 + (u & 1) * 64;
          if (u == 4) {
            mbar_wait(b_x(sb, 0), 0);
          } else {
            mbar_wait(b_empty(sb, slot), slot == 4 ? par ^ 1 : par);
          }
          const uint32_t a = sb + slot * SLOT2, fb = b_full(sb, slot);
          mbar_expect_tx(fb, SLOT2);
          tma2_mc(a + 16384 + rank * 10240, im ? &maps.cim : &maps.cre, ch, g * N2 + rank * 80, fb);
          if ((u & 3) == 0) {
            if (u == 0) { cnt_wait(p.scr, C_HS + mi, gen0 * 4); fence_async_global(); } else mbar_wait(b_ready(sb, u >> 2), 0);
          }
          tma3(a, &maps.hsl, 0, im * DM + ch, mi * 2, fb);
          if (++slot == 5) { slot = 0; par ^= 1; }
        }
        mbar_wait(b_freed(sb, 4), 0);
      }
      const uint32_t fin = sb + (is_ffn ? 4 * SLOT : S_STAGE), genp = load_gen(p);
      mbar_expect_tx(b_x(sb, 1), 20480 + 320);
      tma5(fin, &maps.xf, mi * 16 + (is_ffn ? 0 : 2), g * 5, b_x(sb, 1));
      mbar_expect_tx(b_x(sb, 2), 12288);
      mbar_expect_tx(b_x(sb, 3), 8192);
#pragma unroll 1
      for (int i = 0; i < 3; i++) {
        if (i) { cnt_wait(p.scr, C_Y + (g * 16 + mi) * 2 + !is_ffn, genp * 2 - 2 + i); fence_async_global(); }
        bulk_ld(i ? fin + 8192 + i * 12288 : sb + (is_ffn ? F_CS : S_STAGE + 40960),
                i ? (const void*)(p.scr->simg + ((g * 16 + mi) * 2 + !is_ffn) * 1280 + (i - 1) * 768) : (const void*)(p.dskip + g * N2),
                i ? 16384 - i * 4096 : 320, b_x(sb, 1 + i));
      }
      p.gen[blockIdx.x] = genp + 1;
    } else if (wi == 2) {
      const uint32_t gen = load_gen(p);
      const int ln = t - 64;
#pragma unroll 1
      for (int i = 0; i < 3; i++) {
        const int job = i >> 1;
        if (i == !is_ffn) {
          const uint2* ps = p.scr->stats + mi * 128 + ln;
          const uint2* pq[4] = {ps, ps + 32, ps + 64, ps + 96};
          uint32_t sv[4];
          ld_tags<4>(pq, sv, gen);
#pragma unroll
          for (int k = 0; k < 4; k++) {
            const float rs = rcp_fast(bf_hi(sv[k]));
            sts64(sb + SM_STATS + (k * 32 + ln) * 8, make_float2(bf_lo(sv[k]), rs));
            if (!is_ffn) sts64(sb + S_STATN + ((ln >> 1) * 8 + k * 2 + (ln & 1)) * 8, make_float2(-bf_lo(sv[k]), rs));
          }
        } else {
          const uint2* pa = p.scr->cs + ((is_ffn ? 0 : 8) + g * 2 + job) * 192 + ln;
          const uint2* pp[6] = {pa, pa + 32, pa + 64, pa + 96, pa + 128, pa + 160};
          uint32_t pv[6];
          ld_tags<6>(pp, pv, gen);
          const uint32_t a = is_ffn ? sb + F_CS + (job * N1 + ((ln >> 1) & 3) * (N1 / 4) + (ln >> 3) * 2 + (ln & 1)) * 4 : sb + (job ? S_TAB1 : S_TAB0) + ln * TABP;
          const uint32_t as = is_ffn ? 32 : 32 * TABP, ab = is_ffn ? 96 : 4;
#pragma unroll
          for (int k = 0; k < 6; k++)
            if (k % 3 < 2 || is_ffn || !job) sts32(a + (k % 3) * as + (k / 3) * ab, __uint_as_float(pv[k]));
        }
        __syncwarp();
        if (ln == 0 && i) { mbar_arrive(b_tab(sb, job)); }
      }
    } else if (wi == 1) {
      if (is_ffn) {
#pragma unroll 1
        for (int pc = 0; pc < 4; pc++) {
#pragma unroll 1
          for (int i = 0; i < 3; i++) {
            mbar_wait_lazy(b_staged(sb, i), pc & 1);
            tma3_st(&maps.h1s, sb + F_STAGE + i * 8192, mi * 128, (pc * 4 + g) * 3 + i);
            bulk_commit();
            bulk_wait_read();
            mbar_arrive(b_freed(sb, i));
          }
          if (pc & 1) mbar_arrive(b_freed(sb, 3 + (pc >> 1)));
          bulk_wait_all();
          cnt_signal(p.scr, C_H1 + pc * 16 + mi);
        }
      } else {
#pragma unroll 1
        for (int pc = 0; pc < 5; pc++) {
          mbar_wait_lazy(b_staged(sb, pc), 0);
#pragma unroll 1
          for (int i = 0; i < 2; i++) {
            tma3_st(&maps.hss, sb + S_STAGE + (pc & 1) * 16384 + i * 8192, i * DM + pc * 128 + g * 32, mi * 4);
            bulk_commit();
            if (pc || i) bulk_wait_read();
          }
          mbar_arrive(b_freed(sb, pc));
          if (pc == 2) { mbar_arrive_cluster(b_x(sb, 0), 0); mbar_arrive_cluster(b_x(sb, 0), 1); }
          bulk_wait_all();
          cnt_signal(p.scr, C_HS + pc * 16 + mi);
        }
      }
      mbar_wait(b_staged(sb, 5), 0);
      bulk_st(p.scr->simg + ((g * 16 + mi) * 2 + is_ffn) * 1280, sb + (is_ffn ? F_STAGE : 0), 12288);
      bulk_commit();
      bulk_st(p.scr->simg + ((g * 16 + mi) * 2 + is_ffn) * 1280 + 768, sb + (is_ffn ? F_STAGE : 0) + 12288, 8192);
      bulk_commit();
      asm volatile("cp.async.bulk.wait_group 1;" ::: "memory");
      cnt_signal(p.scr, C_Y + (g * 16 + mi) * 2 + is_ffn);
      bulk_wait_all();
      cnt_signal(p.scr, C_Y + (g * 16 + mi) * 2 + is_ffn);
    } else {
      const uint32_t gen = load_gen(p);
      {
        mbar_wait(b_full(sb, 3), 0);
        if (is_ffn) { prefetch_tmap(&maps.h1s); prefetch_tmap(&maps.h1l); prefetch_tmap(&maps.w2); }
        else { prefetch_tmap(&maps.hss); prefetch_tmap(&maps.hsl); prefetch_tmap(&maps.cre); prefetch_tmap(&maps.cim); }
        prefetch_tmap(&maps.xf);
      }
#pragma unroll 1
      for (int i = !is_ffn; i < 5 - is_ffn; i++) {
        cnt_wait(p.scr, (is_ffn ? C_H1 : C_HS) + i * 16 + mi, gen * 4);
        fence_async_global();
        mbar_arrive(b_ready(sb, i));
      }
    }
  } else {
    const int w = __shfl_sync(0xffffffffu, t >> 5, 0), lane = t & 31, l = lane >> 2, q = lane & 3;
    const int wbar = BAR_WG0 + wg;
    cluster_arrive();
    uint32_t gen = load_gen(p);
    if (!is_ffn && t < 96 - 32 * wg) {
      const int c = wg * 96 + t, ch = (c >> 5) * 128 + g * 32 + (c & 31);
      const float lr = bf_lo(__ldg(reinterpret_cast<const unsigned short*>(p.lre) + ch)), li = bf_lo(__ldg(reinterpret_cast<const unsigned short*>(p.lim) + ch));
      const float dt = bf_round(expf(bf_lo(__ldg(reinterpret_cast<const unsigned short*>(p.logdt) + ch))));
      float sn, cn;
      const float an = dt * li;
      sincospif(fmaf(an, 0.31830987334251404f, an * 1.2841276486597053e-8f), &sn, &cn);
      const float ex = expf(dt * lr);
      float2 l1 = make_float2(ex * cn, ex * sn);
      const float den = 2.0f * rcp_fast(lr * lr + li * li), nr = l1.x - 1.0f, ni = l1.y;
      const float cr = (nr * lr + ni * li) * den, ci = (ni * lr - nr * li) * den;
      if (p.swap) l1.y = -l1.y;
      const uint32_t tb = sb + (wg ? S_TAB1 : S_TAB0) + t * TABP;
      sts64(tb + 8, l1);
      sts128(tb + 32, p.swap ? make_float4(-ci, cr, -cr, -ci) : make_float4(cr, -ci, -ci, -cr));
      float2 l32 = l1;
#pragma unroll 1
      for (int i = 0; i < 5; i++) l32 = cmul(l32, l32);
      const float2 l64 = cmul(l32, l32), L = cmul(l64, l64), l96 = cmul(l64, l32), L2 = cmul(L, L), L4 = cmul(L2, L2), L8 = cmul(L4, L4), L12 = cmul(L8, L4);
      sts128(tb + 16, make_float4(l32.x, l32.y, l64.x, l64.y));
      sts64(tb + 48, L);
      sts128(tb + 64, make_float4(1.f, 0.f, 1.f, 0.f));
      sts128(tb + 80, make_float4(l32.x, l32.y, L4.x, L4.y));
      sts128(tb + 96, make_float4(l64.x, l64.y, L8.x, L8.y));
      sts128(tb + 112, make_float4(l96.x, l96.y, L12.x, L12.y));
    }
    __syncwarp();
    cluster_wait();
    asm volatile("setmaxnreg.inc.sync.aligned.u32 232;");
    auto row2 = [&]() { const int tt = opaque(t); return ((tt >> 5) & 1) * 64 + (tt >> 6) * 8 + ((tt & 31) >> 2); };

    if (wg == 1) {
      if (is_ffn) {
        const int idx = g * 16 + mi;
        const uint32_t abuf = sb + F_STAGE;
#pragma unroll 1
        for (int k = 0; k < 2; k++) {
          if (w == 0 && elect_one()) {
            if (k == 0) {
              mbar_wait(b_full(sb, 0), 0);
              mbar_expect_tx(b_aux(sb), 15360);
              bulk_ld(abuf, (idx < 32 ? p.bre : p.bim) + (size_t)(idx & 31) * 12 * DM, 15360, b_aux(sb));
            } else {
              mbar_expect_tx(b_aux(sb), 20480);
#pragma unroll 1
              for (int i = 0; i < 5; i++) tma2(abuf + i * 4096, &maps.w1s, idx * 16, i * 128, b_aux(sb));
            }
          }
          mbar_wait(b_aux(sb), k);
          const uint32_t aa = k ? abuf + t * 16 : abuf + min(t >> 3, 11) * 1280 + (t & 7) * 16, ast = k ? 2048 : 128;
          float s[8] = {0, 0, 0, 0, 0, 0, 0, 0};
#pragma unroll 5
          for (int i = 0; i < 10; i++) {
            const float4 u = lds128(aa + i * ast);
            add8(s, make_uint4(__float_as_uint(u.x), __float_as_uint(u.y), __float_as_uint(u.z), __float_as_uint(u.w)));
          }
          if (k) {
            sts128(abuf + 20480 + t * 32, make_float4(s[0], s[1], s[2], s[3]));
            sts128(abuf + 20480 + t * 32 + 16, make_float4(s[4], s[5], s[6], s[7]));
          }
          bar_sync(wbar, 128);
          if (k) {
#pragma unroll
            for (int i = 0; i < 8; i++) s[i] = lds32(abuf + 20480 + ((t & 7) * 8 + i) * 64 + (t >> 3) * 4);
          }
          float a = ((s[0] + s[1]) + (s[2] + s[3])) + ((s[4] + s[5]) + (s[6] + s[7]));
#pragma unroll
          for (int o = 1; o < 8; o <<= 1) a += __shfl_xor_sync(0xffffffffu, a, o);
          if ((t & 7) == 0 && (k || t < 96))
            st_tag(p.scr->cs + (k ? cs_slot_w(idx * 16 + (t >> 3)) : cs_slot_b((idx & 31) * 12 + (t >> 3), (idx >> 5) ^ p.swap)), __float_as_uint(a), gen);
        }
        bar_sync(wbar, 128);
      } else {
        float sm[2] = {0.f, 0.f}, sq[2] = {0.f, 0.f};
        const uint32_t ra = sb + ((t >> 3) * 8 + g * 2 + ((t >> 2) & 1)) * 128 + (t & 3) * 32 + ((t >> 2) & 1) * 16;
#pragma unroll 1
        for (int k = 0; k < 10; k++) {
          const int slot = k & 3;
          mbar_wait(b_full(sb, slot), (k >> 2) & 1);
          const float4 u[2] = {lds128(ra + slot * SLOT), lds128((ra ^ 16) + slot * SLOT)};
          bar_sync(wbar, 128);
          if (t < 2) mbar_arrive_cluster(b_empty(sb, slot), t);
#pragma unroll
          for (int i = 0; i < 2; i++) {
            const uint32_t wv[4] = {__float_as_uint(u[i].x), __float_as_uint(u[i].y), __float_as_uint(u[i].z), __float_as_uint(u[i].w)};
#pragma unroll
            for (int j = 0; j < 4; j++) {
              const float a = bf_lo(wv[j]), c = bf_hi(wv[j]);
              sm[0] += a; sm[1] += c; sq[0] = fmaf(a, a, sq[0]); sq[1] = fmaf(c, c, sq[1]);
            }
          }
        }
        float sum = sm[0] + sm[1], ssq = sq[0] + sq[1];
#pragma unroll
        for (int o = 1; o < 4; o <<= 1) { sum += __shfl_xor_sync(0xffffffffu, sum, o); ssq += __shfl_xor_sync(0xffffffffu, ssq, o); }
        const float mean = sum * (1.0f / DM), var = fmaxf(fmaf(-mean, mean, ssq * (1.0f / DM)), 0.f);
        if ((t & 3) == 0) st_tag(p.scr->stats + mi * 128 + g * 32 + (t >> 2), pack_bf16(mean, __fsqrt_rn(bf_round(bf_round(var) + 1e-5f))), gen);
      }
      if (t == 0) mbar_arrive(b_tab(sb, 0));
      bar_sync(BAR_T1, 256);
    }

    float af[80];
    if (is_ffn) {
      constexpr int NT = 45;
      {
        float acc[2][N1 / 2];
        mma_job<N1, 2, 0, F_NSLOT, true>(acc, sb, wg * 10, 10, NT, 4, wg ? BAR_T2 : BAR_T1, t);
        mbar_wait(b_tab(sb, wg), 0);
        float nm[4];
#pragma unroll
        for (int i = 0; i < 4; i++) nm[i] = -lds32(sb + SM_STATS + ((i >> 1) * 64 + w * 16 + l + (i & 1) * 8) * 8);
        if (wg) mbar_wait(b_freed(sb, 3), 0);
        const uint32_t csa = sb + F_CS + wg * (N1 * 4) + q * N1;
        float2 cs[N1 / 8];
#pragma unroll
        for (int j = 0; j < 4; j++) cs[j] = lds64v(csa + j * 8);
        const uint32_t so = sb + F_STAGE + (w * 16 + l) * 64 + ((q ^ (l >> 1)) << 4);
        uint32_t pk[16];
#pragma unroll
        for (int j = 0; j < N1 / 8; j++) {
          if (j + 4 < N1 / 8) cs[j + 4] = lds64v(csa + (j + 4) * 8);
#pragma unroll
          for (int i = 0; i < 4; i++) {
            const float* v = &acc[i >> 1][4 * j + 2 * (i & 1)];
            pk[4 * i + (j & 3)] = pack_bf16_relu(fmaf(nm[i], cs[j].x, v[0]), fmaf(nm[i], cs[j].y, v[1]));
          }
          if ((j & 3) == 3) {
            const int a = j >> 2;
            if (a) staged(b_staged(sb, (a - 1) % 3), t);
            if (a >= 3) mbar_wait(b_freed(sb, a - 3), 0);
#pragma unroll
            for (int i = 0; i < 4; i++) sts128u(so + (a % 3) * 8192 + (i >> 1) * 4096 + (i & 1) * 512, pk[4 * i], pk[4 * i + 1], pk[4 * i + 2], pk[4 * i + 3]);
          }
        }
        staged(b_staged(sb, 2), t);
      }
      if (opaque(wg)) return;
      float acc[2][N2 / 2];
      bar_sync(BAR_T2, 256);
      mma_job<N2, 2, 0, F_NSLOT, false>(acc, sb, 20, 20, NT, 4, 0, t);
      const uint32_t s16 = (sb & 0x3FFFF) >> 4;
#pragma unroll
      for (int mb = 1; mb >= 0; mb--) {
#pragma unroll
        for (int sl = 0; sl < 4; sl++) {
          if (mb == 1) mbar_wait(b_full(sb, sl), 0);
          const uint32_t s0 = s16 + sl * (SLOT >> 4);
          wg_fence();
#pragma unroll
          for (int kk = 0; kk < 4; kk++)
            wgmma<N2, 0, 1>(acc[mb], mkdesc(s0 + mb * 512 + kk * 2, 16, 1024, 1), mkdesc(s0 + 1024 + (((kk >> 1) * (N2 * 64) + (kk & 1) * 1024) >> 4), 2048, 512, 2), 1);
        }
        wg_commit();
        if (mb == 1) {
          wg_wait<1>();
          if (t < 4) mbar_arrive_cluster(b_empty(sb, 4), t & 1);
          mbar_wait(b_freed(sb, 4), 0);
          wg_wait<0>();
          stage_tile(acc[1], sb + F_STAGE, t);
        }
      }
      staged(b_staged(sb, 5), t);
      wg_wait<0>();
#pragma unroll
      for (int i = 0; i < 80; i++) af[i] = acc[0][i];
    } else {
      float acc1[3][64];
      if (wg == 1) {
        mma_job<128, 2, 1, S_NSLOT, true>(*reinterpret_cast<float (*)[2][64]>(&acc1[0][0]), sb, 10, 10, 40, 4, BAR_T2, t);
      } else {
        mma_job<128, 3, 1, S_NSLOT, true>(acc1, sb, 0, 10, 40, 2, BAR_T1, t);
      }
      bar_sync(BAR_TAB + wg * 2, 128);
      mbar_wait(b_tab(sb, wg), 0);
      scan_blocks(acc1, p, sb, opaque(wg), g, mi, w, l, q, gen);
      if (opaque(wg)) return;
      float acc[2][N2 / 2];
      bar_sync(BAR_T2, 256);
      mma_job<N2, 2, 2, 5, false>(acc, sb, 0, 16, 20, 4, 0, t);
      const uint32_t s16 = (sb & 0x3FFFF) >> 4;
#pragma unroll
      for (int mb = 0; mb < 2; mb++) {
#pragma unroll
        for (int sl = 1; sl < 5; sl++) {
          if (mb == 0) mbar_wait(b_full(sb, sl), sl == 4);
          const uint32_t s0 = s16 + sl * (SLOT2 >> 4);
          wg_fence();
#pragma unroll
          for (int kk = 0; kk < 4; kk++) wgmma<N2, 1, 0>(acc[mb], mkdesc(s0 + mb * 512 + kk * 128, 16, 1024, 1), mkdesc(s0 + 1024 + kk * 2, 16, 1024, 1), 1);
        }
        wg_commit();
        if (mb == 0) {
          wg_wait<1>();
          bar_sync(wbar, 128);
          wg_wait<0>();
          stage_tile(acc[0], sb, t);
        }
      }
      staged(b_staged(sb, 5), t);
      wg_wait<0>();
#pragma unroll
      for (int i = 0; i < 80; i++) af[i] = acc[1][i];
    }

    {
      const bool rf = opaque(is_ffn);
      const int r0 = row2() + (rf ? 0 : 16);
      const float2 st0 = lds64(sb + SM_STATS + r0 * 8), st1 = lds64(sb + SM_STATS + (r0 + 32) * 8);
      const float mr0 = -st0.x * st0.y, mr1 = -st1.x * st1.y, z0 = 0.5f * st0.y, z1 = 0.5f * st1.y;
      const int tt = opaque(t), r = (tt >> 5) * 16 + (tt & 15), hi = (tt >> 4) & 1, sw = (r >> 1) & 3;
      const uint32_t fin = sb + (rf ? 4 * SLOT : S_STAGE), da = sb + (rf ? F_CS : S_STAGE + 40960) + (tt & 3) * 4;
      const uint32_t xa0 = fin + r * 64 + ((hi ^ sw) << 4), xa1 = fin + r * 64 + (((2 + hi) ^ sw) << 4);
      float* op = p.out + (size_t)(mi * 128 + r0) * DM + g * N2 + (tt & 3) * 2;
      mbar_wait(b_x(sb, 1), 0);
      float ah[48];
#pragma unroll
      for (int i = 0; i < 48; i++) ah[i] = af[i];
#pragma unroll 1
      for (int hf = 0; hf < 2; hf++) {
        mbar_wait(b_x(sb, 2 + hf), 0);
#pragma unroll
        for (int i = 0; i < 6; i++) {
          if (i < 4 || !hf) {
            uint32_t xw[4];
            asm volatile("ldmatrix.sync.aligned.m8n8.x4.shared.b16 {%0,%1,%2,%3}, [%4];" : "=r"(xw[0]), "=r"(xw[1]), "=r"(xw[2]), "=r"(xw[3]) : "r"(((i & 1) ? xa1 : xa0) + hf * 12288 + (i >> 1) * 4096));
            const uint32_t dk[2] = {__float_as_uint(lds32(da + hf * 192 + i * 32)), __float_as_uint(lds32(da + hf * 192 + i * 32 + 16))};
            const float4 sf = lds128(fin + 20480 + hf * 12288 + (i * 128 + tt) * 16);
            const uint32_t sv[4] = {__float_as_uint(sf.x), __float_as_uint(sf.y), __float_as_uint(sf.z), __float_as_uint(sf.w)};
#pragma unroll
            for (int u = 0; u < 4; u++) {
              const float x0 = bf_lo(xw[u]), x1 = bf_hi(xw[u]), rs = (u & 1) ? st1.y : st0.y, mr = (u & 1) ? mr1 : mr0;
              const float a0 = ah[8 * i + 2 * u], a1 = ah[8 * i + 2 * u + 1], b0 = bf_lo(sv[u]), b1 = bf_hi(sv[u]);
              const float h0 = (rf ? a0 : b0) * ((u & 1) ? z1 : z0), h1 = (rf ? a1 : b1) * ((u & 1) ? z1 : z0);
              const float y0 = fmaf(fmaf(x0, rs, mr), bf_lo(dk[u >> 1]), rf ? b0 : a0), y1 = fmaf(fmaf(x1, rs, mr), bf_hi(dk[u >> 1]), rf ? b1 : a1);
              *reinterpret_cast<float2*>(op + (u & 1) * 32 * DM + (2 * i + (u >> 1)) * 8) =
                  make_float2(fmaf(y0, fmaf(h0, tanh_fast(h0), h0), x0), fmaf(y1, fmaf(h1, tanh_fast(h1), h1), x1));
            }
          }
        }
        op += 96;
#pragma unroll
        for (int i = 0; i < 32; i++) ah[i] = af[48 + i];
      }
    }
  }
}

typedef CUresult (*EncodeFn)(CUtensorMap*, CUtensorMapDataType, cuuint32_t, void*, const cuuint64_t*, const cuuint64_t*, const cuuint32_t*,
                             const cuuint32_t*, CUtensorMapInterleave, CUtensorMapSwizzle, CUtensorMapL2promotion, CUtensorMapFloatOOBfill);

void encode(EncodeFn fn, CUtensorMap* tm, const void* base, int nd, const cuuint64_t* dims, const cuuint64_t* strides, const cuuint32_t* box, CUtensorMapSwizzle sw) {
  const cuuint32_t es[5] = {1, 1, 1, 1, 1};
  fn(tm, CU_TENSOR_MAP_DATA_TYPE_BFLOAT16, nd, const_cast<void*>(base), dims, strides, box, es, CU_TENSOR_MAP_INTERLEAVE_NONE, sw,
     CU_TENSOR_MAP_L2_PROMOTION_L2_128B, CU_TENSOR_MAP_FLOAT_OOB_FILL_NONE);
}
void encode2(EncodeFn fn, CUtensorMap* tm, const void* base, int inner, int outer, int bi, int bo) {
  const cuuint64_t d[2] = {(cuuint64_t)inner, (cuuint64_t)outer}, s[1] = {(cuuint64_t)inner * 2};
  const cuuint32_t b[2] = {(cuuint32_t)bi, (cuuint32_t)bo};
  encode(fn, tm, base, 2, d, s, b, CU_TENSOR_MAP_SWIZZLE_128B);
}
void encode4(EncodeFn fn, CUtensorMap* tm, const void* base, int d0, int d1, int d2, int d3, cuuint64_t s1, cuuint64_t s2, cuuint64_t s3, int b3) {
  const cuuint64_t d[4] = {(cuuint64_t)d0, (cuuint64_t)d1, (cuuint64_t)d2, (cuuint64_t)d3}, s[3] = {s1, s2, s3};
  const cuuint32_t b[4] = {64, (cuuint32_t)d1, (cuuint32_t)d2, (cuuint32_t)b3};
  encode(fn, tm, base, 4, d, s, b, CU_TENSOR_MAP_SWIZZLE_128B);
}

}

extern "C" void kernel_launch(void* const* d_in, const int* in_sizes, int n_in, void* d_out, int out_size) {
  static Maps maps;
  static void *scr = nullptr, *gen = nullptr, *h1 = nullptr, *hs = nullptr;
  static const void* keyp[12];
  static int topo = 0;
  static bool have = false;
  bool same = have;
  for (int i = 0; i < 12; i++) same = same && keyp[i] == d_in[i];
  const char *bre = (const char*)d_in[3], *bim = (const char*)d_in[4];
  if (!same) {
    void* fp = nullptr;
    cudaDriverEntryPointQueryResult qr;
    cudaGetDriverEntryPoint("cuTensorMapEncodeTiled", &fp, cudaEnableDefault, &qr);
    EncodeFn fn = (EncodeFn)fp;
    cudaGetSymbolAddress(&h1, g_H1);
    cudaGetSymbolAddress(&hs, g_Hs);
    cudaGetSymbolAddress(&scr, g_scr);
    cudaGetSymbolAddress(&gen, g_gen);
    constexpr cuuint64_t RX = DM * 2, RH = DFF * 2;
    encode2(fn, &maps.x, d_in[0], DM, SEQ, 64, 128);
    encode4(fn, &maps.xp, d_in[0], DM, 2, 4, SEQ / 2, RX, 32 * RX, 2 * RX, 16);
    encode4(fn, &maps.bb, bre < bim ? bre : bim, DM, 8, 2, DM / 8, RX, (cuuint64_t)(bre < bim ? bim - bre : bre - bim), 8 * RX, 2);
    {
      const cuuint64_t d[5] = {DM, 8, 2, 16, 5}, s[4] = {RX, (cuuint64_t)(bre < bim ? bim - bre : bre - bim), 8 * RX, 128 * RX};
      const cuuint32_t b[5] = {64, 8, 2, 4, 3};
      encode(fn, &maps.bb0, bre < bim ? bre : bim, 5, d, s, b, CU_TENSOR_MAP_SWIZZLE_128B);
    }
    encode2(fn, &maps.cre, d_in[5], DM, DM, 64, 80);
    encode2(fn, &maps.cim, d_in[6], DM, DM, 64, 80);
    {
      const cuuint64_t d[5] = {32, DM, 3, 2, 12}, s[4] = {RH, 64, 768, 192};
      const cuuint32_t b[5] = {32, 32, 3, 2, 1};
      encode(fn, &maps.w1, d_in[10], 5, d, s, b, CU_TENSOR_MAP_SWIZZLE_64B);
    }
    {
      const cuuint64_t d[5] = {32, 2, DFF / 8, 4, DM / 32}, s[4] = {RX, 8 * RX, 2 * RX, 64};
      const cuuint32_t b[5] = {32, 2, 4, 4, N2 / 32};
      encode(fn, &maps.w2, d_in[11], 5, d, s, b, CU_TENSOR_MAP_SWIZZLE_64B);
    }
    encode4(fn, &maps.h1l, h1, DFF, 8, 4, SEQ / 8, RH, 32 * RH, 8 * RH, 4);
    {
      const cuuint64_t d[3] = {64, 2 * DM, SEQ / 64}, s[2] = {HSP * 2, 128};
      const cuuint32_t b[3] = {64, 64, 2};
      encode(fn, &maps.hsl, hs, 3, d, s, b, CU_TENSOR_MAP_SWIZZLE_128B);
    }
    {
      const cuuint64_t d[2] = {DFF, DM}, s[1] = {RH};
      const cuuint32_t b[2] = {16, 128};
      encode(fn, &maps.w1s, d_in[10], 2, d, s, b, CU_TENSOR_MAP_SWIZZLE_NONE);
    }
    {
      const cuuint64_t d[5] = {32, 8, 4, SEQ / 8, DM / 32}, s[4] = {RX, 32 * RX, 8 * RX, 64};
      const cuuint32_t b[5] = {32, 8, 4, 2, N2 / 32};
      encode(fn, &maps.xf, d_in[0], 5, d, s, b, CU_TENSOR_MAP_SWIZZLE_64B);
    }
    {
      const cuuint64_t d[3] = {32, SEQ, DFF / 32}, s[2] = {RH, 64}, d2[3] = {32, 2 * DM, SEQ / 32}, s2[2] = {HSP * 2, 64};
      const cuuint32_t b[3] = {32, 128, 1}, b2[3] = {32, 32, 4};
      encode(fn, &maps.h1s, h1, 3, d, s, b, CU_TENSOR_MAP_SWIZZLE_64B);
      encode(fn, &maps.hss, hs, 3, d2, s2, b2, CU_TENSOR_MAP_SWIZZLE_64B);
    }
    cudaFuncSetAttribute(s5_ffn_fused, cudaFuncAttributeMaxDynamicSharedMemorySize, SMEM_BYTES);
    cudaLaunchConfig_t qc = {};
    qc.gridDim = dim3(8); qc.blockDim = dim3(384); qc.dynamicSmemBytes = SMEM_BYTES;
    cudaLaunchAttribute qa[1];
    qa[0].id = cudaLaunchAttributeClusterDimension; qa[0].val.clusterDim.x = 8; qa[0].val.clusterDim.y = 1; qa[0].val.clusterDim.z = 1;
    qc.attrs = qa; qc.numAttrs = 1;
    int nc8 = 0;
    if (cudaOccupancyMaxActiveClusters(&nc8, s5_ffn_fused, &qc) != cudaSuccess) (void)cudaGetLastError();
    topo = nc8 == 15;
    for (int i = 0; i < 12; i++) keyp[i] = d_in[i];
    have = true;
  }
  Ptrs p;
  p.x = (const __nv_bfloat16*)d_in[0]; p.lre = (const __nv_bfloat16*)d_in[1]; p.lim = (const __nv_bfloat16*)d_in[2];
  p.bre = (const __nv_bfloat16*)d_in[3]; p.bim = (const __nv_bfloat16*)d_in[4]; p.logdt = (const __nv_bfloat16*)d_in[7];
  p.dskip = (const __nv_bfloat16*)d_in[8]; p.w1 = (const __nv_bfloat16*)d_in[10];
  p.out = (float*)d_out;
  p.scr = (Scratch*)scr; p.gen = (unsigned*)gen; p.swap = bim < bre; p.topo = topo; p.zero = 0;
  cudaLaunchConfig_t cfg = {};
  cfg.gridDim = dim3(NCTA); cfg.blockDim = dim3(384); cfg.dynamicSmemBytes = SMEM_BYTES; cfg.stream = cudaStreamPerThread;
  cudaLaunchAttribute at[1];
  at[0].id = cudaLaunchAttributeClusterDimension; at[0].val.clusterDim.x = 2; at[0].val.clusterDim.y = 1; at[0].val.clusterDim.z = 1;
  cfg.attrs = at; cfg.numAttrs = 1;
  cudaLaunchKernelEx(&cfg, s5_ffn_fused, p, maps);
}
```
